```python
import torch

def _softmax(x, axis=-1):
    return torch.softmax(x, dim=axis)
def _gelu(x):
    return torch.nn.functional.gelu(x, approximate="tanh")
def _silu(x):
    return torch.nn.functional.silu(x)
def _sigmoid(x):
    return torch.sigmoid(x)
def _layernorm(x, axis=-1, eps=1e-5):
    m = x.mean(dim=axis, keepdim=True)
    v = x.var(dim=axis, keepdim=True, unbiased=False)
    return (x - m) / torch.sqrt(v + eps)
def _scatter_add(tgt, idx, src, axis=0):
    return tgt.clone().index_add_(axis, idx, src)
def _segment_sum(src, seg, n):
    out = torch.zeros((n,) + src.shape[1:], dtype=src.dtype)
    return out.index_add_(0, seg, src)
def _pad(x, pw):
    flat = tuple(v for pair in reversed(pw) for v in pair)
    return torch.nn.functional.pad(x, flat)

kernel_name = 'gated_mix__grouped_kv_mqa__ssm_conv_s4__prompt'

def setup_inputs():

    _w = (lambda a: (lambda t: t.to(torch.bfloat16) if t.is_floating_point() else t)(torch.as_tensor(a)))
    def _A_setup():
        B, S, D, H = 1, 2048, 448, 16
        Dh = D // H
        return {
            "x": _w((lambda *s: torch.randn(*s, dtype=torch.bfloat16) * 0.05)(B, S, D)),
            "wq": _w((lambda *s: torch.randn(*s, dtype=torch.bfloat16) * 1.6)(D, H * Dh)),
            "wk": _w((lambda *s: torch.randn(*s, dtype=torch.bfloat16) * 1.6)(D, Dh)),
            "wv": _w((lambda *s: torch.randn(*s, dtype=torch.bfloat16) * 0.05)(D, Dh)),
            "wo": _w((lambda *s: torch.randn(*s, dtype=torch.bfloat16) * 0.05)(H * Dh, D)),
        }
    _A_in = _A_setup()

    def _B_setup():
        B, L, D, N = 1, 2048, 448, 256
        A_re = -(lambda _x: torch.exp(torch.as_tensor(_x)))((lambda *s: torch.randn(*s, dtype=torch.bfloat16) * 3.2)(D, N))
        A_im = torch.pi * (lambda *s: torch.randn(*s, dtype=torch.bfloat16) * 0.05)(D, N)
        B_re = (lambda *s: torch.randn(*s, dtype=torch.bfloat16) * 0.2)(D, N)
        B_im = (lambda *s: torch.randn(*s, dtype=torch.bfloat16) * 0.2)(D, N)
        C_re = (lambda *s: torch.randn(*s, dtype=torch.bfloat16) * 0.2)(D, N)
        C_im = (lambda *s: torch.randn(*s, dtype=torch.bfloat16) * 0.2)(D, N)
        log_dt = (lambda *s: torch.randn(*s, dtype=torch.bfloat16) * 0.05)(D) * 0.5 - 4.0
        Dskip = (lambda *s: torch.randn(*s, dtype=torch.bfloat16) * 0.1)(D)
        return {
            "u": _w((lambda *s: torch.randn(*s, dtype=torch.bfloat16) * 0.05)(B, L, D)),
            "A_re": _w(A_re),
            "A_im": _w(A_im),
            "B_re": _w(B_re),
            "B_im": _w(B_im),
            "C_re": _w(C_re),
            "C_im": _w(C_im),
            "log_dt": _w(log_dt),
            "Dskip": _w(Dskip),
        }
    _B_in = _B_setup()

    return {
        "A_x": _A_in["x"],
        "A_wq": _A_in["wq"],
        "A_wk": _A_in["wk"],
        "A_wv": _A_in["wv"],
        "A_wo": _A_in["wo"],
        "B_u": _B_in["u"],
        "B_A_re": _B_in["A_re"],
        "B_A_im": _B_in["A_im"],
        "B_B_re": _B_in["B_re"],
        "B_B_im": _B_in["B_im"],
        "B_C_re": _B_in["C_re"],
        "B_C_im": _B_in["C_im"],
        "B_log_dt": _B_in["log_dt"],
        "B_Dskip": _B_in["Dskip"],
        "gate_w": _w((lambda *s: torch.randn(*s, dtype=torch.bfloat16) * 0.05)(448) * 16.0),
    }

def reference(A_x, A_wq, A_wk, A_wv, A_wo, B_u, B_A_re, B_A_im, B_B_re, B_B_im, B_C_re, B_C_im, B_log_dt, B_Dskip, gate_w):
    def _A_ref(x, wq, wk, wv, wo):
        B, S, D = x.shape
        H = 16
        Dh = D // H
        q = (lambda x, *d: x.permute(*d))((x @ wq).reshape(B, S, H, Dh), 0, 2, 1, 3)
        k = x @ wk
        v = x @ wv
        scores = torch.einsum("bhqd,bkd->bhqk", q, k) * (Dh ** -0.5)
        p = _softmax(scores, axis=-1)
        o = torch.einsum("bhqk,bkd->bhqd", p, v)
        return (lambda x, *d: x.permute(*d))(o, 0, 2, 1, 3).reshape(B, S, H * Dh) @ wo

    def _B_ref(u, A_re, A_im, B_re, B_im, C_re, C_im, log_dt, Dskip):
        Bsz, L, D = u.shape
        dt = torch.exp(log_dt)[:, None]
        A = A_re + 1j * A_im
        Bc = B_re + 1j * B_im
        Cc = C_re + 1j * C_im
        logdA = dt * A
        dB = dt * Bc
        l = (lambda x, dt: x.to(dt))(torch.arange(L), A_re.dtype)
        P = torch.exp(logdA[:, :, None] * l[None, None, :])
        K = torch.einsum("dn,dnl,dn->dl", Cc, P, dB).real
        L2 = 2 * L
        Kp = _pad(K, ((0, 0), (0, L)))
        up = (lambda x, *d: x.permute(*d))(u, 0, 2, 1)
        up = _pad(up, ((0, 0), (0, 0), (0, L)))
        Kf = (lambda x, axes=(-2,-1): torch.fft.rfft2(x.float(), dim=axes))(Kp[:, None, :], axes=(-2, -1))
        Uf = (lambda x, axes=(-2,-1): torch.fft.rfft2(x.float(), dim=axes))(up[:, :, None, :], axes=(-2, -1))
        Yf = Uf * Kf[None, :, :, :]
        y = (lambda x, s, axes=(-2,-1): torch.fft.irfft2(x, s=s, dim=axes).to(torch.bfloat16))(Yf, (1, L2), axes=(-2, -1))[:, :, 0, :L]
        y = (lambda x, *d: x.permute(*d))(y, 0, 2, 1) + u * Dskip[None, None, :]
        return y

    x = A_x
    g = _sigmoid((x * gate_w).sum(-1, keepdims=True))
    a = _A_ref(x, A_wq, A_wk, A_wv, A_wo)
    b = _B_ref(x, B_A_re, B_A_im, B_B_re, B_B_im, B_C_re, B_C_im, B_log_dt, B_Dskip)
    return g * a + (1 - g) * b
```

```cpp
#include <cuda_runtime.h>
#include <cuda_bf16.h>
#include <cuda_fp16.h>
#include <cuda.h>
#include <stdint.h>

namespace {

constexpr int SEQ = 2048, DM = 448, DH = 28, NST = 256;
constexpr int N_ATT = 128, N_CTA = 132;
#define TID threadIdx.x
constexpr int LOAD_DELAY = 700;

#define MUFU_BITS 0x2222
constexpr uint32_t MUFU_MASK = MUFU_BITS;
constexpr float SAFE_SCORE = 80.0f;

constexpr uint32_t sb = 1024;
constexpr uint32_t SM_X = 0, SM_W = 114688, SM_RAW = 172032, RAW_V = 25088 + 64, RAW_G = RAW_V + 25088;
constexpr uint32_t SM_QR = 16384, SM_E2 = 49152, SM_WO = 0, SM_Q = 86016, SM_KV = 102400;
constexpr uint32_t SM_SSM = 174080, SSM_WG = 28672;
constexpr uint32_t SM_BT = SM_SSM, SM_G = SM_SSM + 14336, SM_OUT = SM_SSM + SSM_WG;
constexpr uint32_t SM_OWN = SM_Q + 1024, SM_WO3 = SM_KV, SM_OR = SM_KV + 28672;
constexpr uint32_t SM_AUX = 172032, SM_ST = 172032, SM_RED = 173056, SM_BAR = SM_SSM + 2 * SSM_WG, SM_TOTAL = SM_BAR + 328;
constexpr uint32_t C_KD = 0, C_V = 2816, V_PL = 1088, C_Y3 = 7168, C_PT = 11776, C_PE = 16256, C_U = 23296, U_LBO = 1312;
constexpr uint32_t C_EX = C_KD, C_OUT = C_Y3, C_E = 20480, C_KD2 = 20480, C_KD3 = 17280;
constexpr uint32_t B_CH = 0, B_KVF = 56, B_KVE = 88, B_QR = 120, B_WO = 128, B_BT = 136, B_O = 144;
constexpr uint32_t B_KA = 168, B_KH = 176, B_XF = 184, B_EPOCH = 192, B_QB = 208, B_RAW = 216, B_WO3 = 224, B_S13 = 232, B_UOK = 240, B_CHK = 248, SM_EPOCH = 200, SM_FLAG = 256, B_ST = 288, B_U = 296;

__device__ uint4 g_uT[DM * 256];
__device__ uint4 g_q[32 * 7 * 512];
__device__ uint4 g_kv[SEQ * 8];
__device__ uint4 g_o[32 * 8 * 448];
__device__ uint4 g_bT[32 * DM * 8];
__device__ __align__(16) float g_gate[SEQ];
__device__ uint4 g_stat[64];
__device__ uint4 g_kd[112 * 161];
constexpr int CT_TICKET = 0, CT_U = 1, CT_KV = 8, CT_B = 9, CT_Q = 13, CT_O = 45, CT_ST = 77, CT_KD = 78, CT_N = 190;
__device__ unsigned g_cnt[CT_N * 32];
#define TS(i) do {} while (0)

struct Params {
  const __nv_bfloat16* ssm[6];
  const __nv_bfloat16 *wk, *wv, *logdt, *dskip, *gatew;
  __nv_bfloat16* out;
  uint32_t k64k;
};

__device__ __forceinline__ void mbar_init(uint32_t b, int c) { asm volatile("mbarrier.init.shared::cta.b64 [%0], %1;" ::"r"(b), "r"(c) : "memory"); }
__device__ __forceinline__ void mbar_expect(uint32_t b, uint32_t tx) { asm volatile("mbarrier.arrive.expect_tx.shared::cta.b64 _, [%0], %1;" ::"r"(b), "r"(tx) : "memory"); }
__device__ __forceinline__ void mbar_arrive(uint32_t b) { asm volatile("mbarrier.arrive.shared::cta.b64 _, [%0];" ::"r"(b) : "memory"); }
__device__ __forceinline__ bool mbar_try(uint32_t b, uint32_t ph) {
  uint32_t ok;
  asm volatile("{ .reg .pred p; mbarrier.try_wait.parity.shared::cta.b64 p, [%1], %2; selp.u32 %0, 1, 0, p; }" : "=r"(ok) : "r"(b), "r"(ph) : "memory");
  return ok;
}
__device__ __forceinline__ void mbar_wait(uint32_t b, uint32_t ph) {
  if (mbar_try(b, ph)) return;
#pragma unroll 1
  for (int i = 0; i < (1 << 20); i++)
    if (mbar_try(b, ph)) return;
  __trap();
}
__device__ __forceinline__ void mbar_arrive_if(uint32_t b, bool on) {
  asm volatile("{ .reg .pred p; setp.ne.u32 p, %1, 0; @p mbarrier.arrive.shared::cta.b64 _, [%0]; }" ::"r"(b), "r"((uint32_t)on) : "memory");
}
__device__ __forceinline__ int warp_in_group() { return __shfl_sync(~0u, (TID >> 5) & 3, 0); }
__device__ __forceinline__ bool elect_one() {
  uint32_t r;
  asm volatile("{ .reg .pred p; elect.sync _|p, 0xffffffff; selp.u32 %0, 1, 0, p; }" : "=r"(r));
  return r;
}
__device__ __forceinline__ void bulk_g2s(uint32_t dst, const void* src, uint32_t bytes, uint32_t b) {
  asm volatile("cp.async.bulk.shared::cluster.global.mbarrier::complete_tx::bytes [%0], [%1], %2, [%3];" ::"r"(dst), "l"(src), "r"(bytes), "r"(b) : "memory");
}
__device__ __forceinline__ void tma2d(uint32_t dst, const CUtensorMap* m, int c0, int c1, uint32_t b) {
  asm volatile("cp.async.bulk.tensor.2d.shared::cluster.global.mbarrier::complete_tx::bytes [%0], [%1, {%3, %4}], [%2];" ::"r"(dst), "l"(m), "r"(b), "r"(c0), "r"(c1) : "memory");
}
__device__ __forceinline__ void tma2d_store(const CUtensorMap* m, uint32_t src, int c0, int c1) {
  asm volatile("cp.async.bulk.tensor.2d.global.shared::cta.bulk_group [%0, {%2, %3}], [%1];" ::"l"(m), "r"(src), "r"(c0), "r"(c1) : "memory");
}
__device__ __forceinline__ void fence_mbar_init() { asm volatile("fence.mbarrier_init.release.cluster;" ::: "memory"); }
__device__ __forceinline__ void fence_async_smem() { asm volatile("fence.proxy.async.shared::cta;" ::: "memory"); }
__device__ __forceinline__ void bar_sync(int id, int n) { asm volatile("bar.sync %0, %1;" ::"r"(id), "r"(n) : "memory"); }
__device__ __forceinline__ void bulk_s2g(void* dst, uint32_t src, uint32_t bytes) {
  asm volatile("cp.async.bulk.global.shared::cta.bulk_group [%0], [%1], %2;" ::"l"(dst), "r"(src), "r"(bytes) : "memory");
}
__device__ __forceinline__ void bulk_drain() {
  asm volatile("cp.async.bulk.commit_group;" ::: "memory");
  asm volatile("cp.async.bulk.wait_group 0;" ::: "memory");
}
__device__ __forceinline__ void cnt_post(int c) { asm volatile("red.relaxed.gpu.global.add.u32 [%0], 1;" ::"l"(&g_cnt[c * 32]) : "memory"); }
__device__ __forceinline__ void cnt_signal(int c) {
  asm volatile("fence.acq_rel.gpu;" ::: "memory");
  cnt_post(c);
}
__device__ __forceinline__ void cnt_wait(int c, uint32_t target) {
#pragma unroll 1
  for (int i = 0; i < (1 << 21); i++) {
    uint32_t v;
    asm volatile("ld.relaxed.gpu.global.u32 %0, [%1];" : "=r"(v) : "l"(&g_cnt[c * 32]) : "memory");
    if ((int)(v - target) >= 0) return;
  }
  __trap();
}
__device__ __forceinline__ uint32_t read_epoch() {
  mbar_wait(sb + SM_BAR + B_EPOCH, 0);
  uint32_t v;
  asm volatile("ld.shared.u32 %0, [%1];" : "=r"(v) : "r"(sb + SM_BAR + SM_EPOCH) : "memory");
  return v + 1;
}
__device__ __forceinline__ void wg_fence() { asm volatile("wgmma.fence.sync.aligned;" ::: "memory"); }
__device__ __forceinline__ void wg_commit() { asm volatile("wgmma.commit_group.sync.aligned;" ::: "memory"); }
template <int N> __device__ __forceinline__ void wg_wait() { asm volatile("wgmma.wait_group.sync.aligned %0;" ::"n"(N) : "memory"); }
template <int N> __device__ __forceinline__ void pin(uint32_t (&d)[N]) {
#pragma unroll
  for (int i = 0; i < N; i++) asm volatile("" : "+r"(d[i])::"memory");
}
template <int N> __device__ __forceinline__ void pin(float (&d)[N]) {
#pragma unroll
  for (int i = 0; i < N; i++) asm volatile("" : "+f"(d[i])::"memory");
}
__host__ __device__ __forceinline__ uint64_t mkdesc(uint32_t addr, uint32_t lbo, uint32_t sbo, uint32_t sw) {
  return (uint64_t)((addr & 0x3FFFF) >> 4) | ((uint64_t)(lbo >> 4) << 16) | ((uint64_t)(sbo >> 4) << 32) | ((uint64_t)sw << 62);
}
__device__ __forceinline__ uint32_t lds32(uint32_t a) { uint32_t v; asm volatile("ld.shared.u32 %0, [%1];" : "=r"(v) : "r"(a) : "memory"); return v; }
__device__ __forceinline__ float lds32f(uint32_t a) { return __uint_as_float(lds32(a)); }
__device__ __forceinline__ uint2 lds64(uint32_t a) { uint2 v; asm volatile("ld.shared.v2.u32 {%0,%1}, [%2];" : "=r"(v.x), "=r"(v.y) : "r"(a) : "memory"); return v; }
__device__ __forceinline__ uint4 lds128(uint32_t a) { uint4 v; asm volatile("ld.shared.v4.u32 {%0,%1,%2,%3}, [%4];" : "=r"(v.x), "=r"(v.y), "=r"(v.z), "=r"(v.w) : "r"(a) : "memory"); return v; }
__device__ __forceinline__ void sts32(uint32_t a, uint32_t v) { asm volatile("st.shared.u32 [%0], %1;" ::"r"(a), "r"(v) : "memory"); }
__device__ __forceinline__ void sts32f(uint32_t a, float v) { sts32(a, __float_as_uint(v)); }
__device__ __forceinline__ void sts64(uint32_t a, uint32_t x, uint32_t y) { asm volatile("st.shared.v2.u32 [%0], {%1,%2};" ::"r"(a), "r"(x), "r"(y) : "memory"); }
__device__ __forceinline__ void sts128(uint32_t a, uint32_t x, uint32_t y, uint32_t z, uint32_t w) { asm volatile("st.shared.v4.u32 [%0], {%1,%2,%3,%4};" ::"r"(a), "r"(x), "r"(y), "r"(z), "r"(w) : "memory"); }
__device__ __forceinline__ void ldsm4t(uint32_t& r0, uint32_t& r1, uint32_t& r2, uint32_t& r3, uint32_t a) {
  asm volatile("ldmatrix.sync.aligned.m8n8.x4.trans.shared.b16 {%0,%1,%2,%3}, [%4];" : "=r"(r0), "=r"(r1), "=r"(r2), "=r"(r3) : "r"(a) : "memory");
}
__device__ __forceinline__ void stsm4t(uint32_t a, uint32_t r0, uint32_t r1, uint32_t r2, uint32_t r3) {
  asm volatile("stmatrix.sync.aligned.m8n8.x4.trans.shared.b16 [%0], {%1,%2,%3,%4};" ::"r"(a), "r"(r0), "r"(r1), "r"(r2), "r"(r3) : "memory");
}
__device__ __forceinline__ void stsm4(uint32_t a, uint32_t r0, uint32_t r1, uint32_t r2, uint32_t r3) {
  asm volatile("stmatrix.sync.aligned.m8n8.x4.shared.b16 [%0], {%1,%2,%3,%4};" ::"r"(a), "r"(r0), "r"(r1), "r"(r2), "r"(r3) : "memory");
}
__device__ __forceinline__ uint32_t pack_bf(float lo, float hi) { uint32_t r; asm("cvt.rn.bf16x2.f32 %0, %1, %2;" : "=r"(r) : "f"(hi), "f"(lo)); return r; }
__device__ __forceinline__ float bf_lo(uint32_t v) { return __uint_as_float(v << 16); }
__device__ __forceinline__ float bf_hi(uint32_t v) { return __uint_as_float(v & 0xffff0000u); }
__device__ __forceinline__ float ex2(float x) { float r; asm("ex2.approx.ftz.f32 %0, %1;" : "=f"(r) : "f"(x)); return r; }
__device__ __forceinline__ void wg_ss64_z(float (&d)[32], uint64_t da, uint64_t db) {
  asm volatile("{ .reg .pred p; setp.ne.b32 p, 0, 0; wgmma.mma_async.sync.aligned.m64n64k16.f32.bf16.bf16 "
    "{%0, %1, %2, %3, %4, %5, %6, %7, %8, %9, %10, %11, %12, %13, %14, %15, %16, %17, %18, %19, %20, %21, %22, %23, %24, %25, %26, %27, %28, %29, %30, %31}, %32, %33, p, 1, 1, 0, 0; }"
    : "=f"(d[0]), "=f"(d[1]), "=f"(d[2]), "=f"(d[3]), "=f"(d[4]), "=f"(d[5]), "=f"(d[6]), "=f"(d[7]), "=f"(d[8]), "=f"(d[9]), "=f"(d[10]), "=f"(d[11]), "=f"(d[12]), "=f"(d[13]), "=f"(d[14]), "=f"(d[15]), "=f"(d[16]), "=f"(d[17]), "=f"(d[18]), "=f"(d[19]), "=f"(d[20]), "=f"(d[21]), "=f"(d[22]), "=f"(d[23]), "=f"(d[24]), "=f"(d[25]), "=f"(d[26]), "=f"(d[27]), "=f"(d[28]), "=f"(d[29]), "=f"(d[30]), "=f"(d[31])
    : "l"(da), "l"(db));
}
__device__ __forceinline__ void wg_ss64(float (&d)[32], uint64_t da, uint64_t db) {
  asm volatile("{ .reg .pred p; setp.ne.b32 p, 1, 0; wgmma.mma_async.sync.aligned.m64n64k16.f32.bf16.bf16 "
    "{%0, %1, %2, %3, %4, %5, %6, %7, %8, %9, %10, %11, %12, %13, %14, %15, %16, %17, %18, %19, %20, %21, %22, %23, %24, %25, %26, %27, %28, %29, %30, %31}, %32, %33, p, 1, 1, 0, 0; }"
    : "+f"(d[0]), "+f"(d[1]), "+f"(d[2]), "+f"(d[3]), "+f"(d[4]), "+f"(d[5]), "+f"(d[6]), "+f"(d[7]), "+f"(d[8]), "+f"(d[9]), "+f"(d[10]), "+f"(d[11]), "+f"(d[12]), "+f"(d[13]), "+f"(d[14]), "+f"(d[15]), "+f"(d[16]), "+f"(d[17]), "+f"(d[18]), "+f"(d[19]), "+f"(d[20]), "+f"(d[21]), "+f"(d[22]), "+f"(d[23]), "+f"(d[24]), "+f"(d[25]), "+f"(d[26]), "+f"(d[27]), "+f"(d[28]), "+f"(d[29]), "+f"(d[30]), "+f"(d[31])
    : "l"(da), "l"(db));
}
__device__ __forceinline__ void wg_rs32t(float (&d)[16], uint32_t a0, uint32_t a1, uint32_t a2, uint32_t a3, uint64_t db) {
  asm volatile("{ .reg .pred p; setp.ne.b32 p, 1, 0; wgmma.mma_async.sync.aligned.m64n32k16.f32.bf16.bf16 "
    "{%0, %1, %2, %3, %4, %5, %6, %7, %8, %9, %10, %11, %12, %13, %14, %15}, {%16,%17,%18,%19}, %20, p, 1, 1, 1; }"
    : "+f"(d[0]), "+f"(d[1]), "+f"(d[2]), "+f"(d[3]), "+f"(d[4]), "+f"(d[5]), "+f"(d[6]), "+f"(d[7]), "+f"(d[8]), "+f"(d[9]), "+f"(d[10]), "+f"(d[11]), "+f"(d[12]), "+f"(d[13]), "+f"(d[14]), "+f"(d[15])
    : "r"(a0), "r"(a1), "r"(a2), "r"(a3), "l"(db));
}
__device__ __forceinline__ void wg_ss64t(float (&d)[32], uint64_t da, uint64_t db) {
  asm volatile("{ .reg .pred p; setp.ne.b32 p, 1, 0; wgmma.mma_async.sync.aligned.m64n64k16.f32.bf16.bf16 "
    "{%0, %1, %2, %3, %4, %5, %6, %7, %8, %9, %10, %11, %12, %13, %14, %15, %16, %17, %18, %19, %20, %21, %22, %23, %24, %25, %26, %27, %28, %29, %30, %31}, %32, %33, p, 1, 1, 0, 1; }"
    : "+f"(d[0]), "+f"(d[1]), "+f"(d[2]), "+f"(d[3]), "+f"(d[4]), "+f"(d[5]), "+f"(d[6]), "+f"(d[7]), "+f"(d[8]), "+f"(d[9]), "+f"(d[10]), "+f"(d[11]), "+f"(d[12]), "+f"(d[13]), "+f"(d[14]), "+f"(d[15]), "+f"(d[16]), "+f"(d[17]), "+f"(d[18]), "+f"(d[19]), "+f"(d[20]), "+f"(d[21]), "+f"(d[22]), "+f"(d[23]), "+f"(d[24]), "+f"(d[25]), "+f"(d[26]), "+f"(d[27]), "+f"(d[28]), "+f"(d[29]), "+f"(d[30]), "+f"(d[31])
    : "l"(da), "l"(db));
}
__device__ __forceinline__ void wg_ss56t(float (&d)[28], uint64_t da, uint64_t db) {
  asm volatile("{ .reg .pred p; setp.ne.b32 p, 1, 0; wgmma.mma_async.sync.aligned.m64n56k16.f32.bf16.bf16 "
    "{%0, %1, %2, %3, %4, %5, %6, %7, %8, %9, %10, %11, %12, %13, %14, %15, %16, %17, %18, %19, %20, %21, %22, %23, %24, %25, %26, %27}, %28, %29, p, 1, 1, 0, 1; }"
    : "+f"(d[0]), "+f"(d[1]), "+f"(d[2]), "+f"(d[3]), "+f"(d[4]), "+f"(d[5]), "+f"(d[6]), "+f"(d[7]), "+f"(d[8]), "+f"(d[9]), "+f"(d[10]), "+f"(d[11]), "+f"(d[12]), "+f"(d[13]), "+f"(d[14]), "+f"(d[15]), "+f"(d[16]), "+f"(d[17]), "+f"(d[18]), "+f"(d[19]), "+f"(d[20]), "+f"(d[21]), "+f"(d[22]), "+f"(d[23]), "+f"(d[24]), "+f"(d[25]), "+f"(d[26]), "+f"(d[27])
    : "l"(da), "l"(db));
}
__device__ __forceinline__ void wg_rs64(float (&d)[32], uint32_t a0, uint32_t a1, uint32_t a2, uint32_t a3, uint64_t db) {
  asm volatile("{ .reg .pred p; setp.ne.b32 p, 1, 0; wgmma.mma_async.sync.aligned.m64n64k16.f32.bf16.bf16 "
    "{%0, %1, %2, %3, %4, %5, %6, %7, %8, %9, %10, %11, %12, %13, %14, %15, %16, %17, %18, %19, %20, %21, %22, %23, %24, %25, %26, %27, %28, %29, %30, %31}, {%32,%33,%34,%35}, %36, p, 1, 1, 0; }"
    : "+f"(d[0]), "+f"(d[1]), "+f"(d[2]), "+f"(d[3]), "+f"(d[4]), "+f"(d[5]), "+f"(d[6]), "+f"(d[7]), "+f"(d[8]), "+f"(d[9]), "+f"(d[10]), "+f"(d[11]), "+f"(d[12]), "+f"(d[13]), "+f"(d[14]), "+f"(d[15]), "+f"(d[16]), "+f"(d[17]), "+f"(d[18]), "+f"(d[19]), "+f"(d[20]), "+f"(d[21]), "+f"(d[22]), "+f"(d[23]), "+f"(d[24]), "+f"(d[25]), "+f"(d[26]), "+f"(d[27]), "+f"(d[28]), "+f"(d[29]), "+f"(d[30]), "+f"(d[31])
    : "r"(a0), "r"(a1), "r"(a2), "r"(a3), "l"(db));
}
__device__ __forceinline__ void wg_rs16t(float (&d)[8], uint32_t a0, uint32_t a1, uint32_t a2, uint32_t a3, uint64_t db) {
  asm volatile("{ .reg .pred p; setp.ne.b32 p, 1, 0; wgmma.mma_async.sync.aligned.m64n16k16.f32.bf16.bf16 "
    "{%0, %1, %2, %3, %4, %5, %6, %7}, {%8,%9,%10,%11}, %12, p, 1, 1, 1; }"
    : "+f"(d[0]), "+f"(d[1]), "+f"(d[2]), "+f"(d[3]), "+f"(d[4]), "+f"(d[5]), "+f"(d[6]), "+f"(d[7])
    : "r"(a0), "r"(a1), "r"(a2), "r"(a3), "l"(db));
}
__device__ __forceinline__ void wg_h16tt(float (&d)[8], uint64_t da, uint64_t db) {
  asm volatile("wgmma.mma_async.sync.aligned.m64n16k16.f32.f16.f16 {%0, %1, %2, %3, %4, %5, %6, %7}, %8, %9, 1, 1, 1, 1, 1;"
    : "+f"(d[0]), "+f"(d[1]), "+f"(d[2]), "+f"(d[3]), "+f"(d[4]), "+f"(d[5]), "+f"(d[6]), "+f"(d[7])
    : "l"(da), "l"(db));
}

struct cplx { float r, i; };
__device__ __forceinline__ cplx cseed(float al, float be, float k) {
  float m = ex2(al * k), a = be * k;
  return {m * __cosf(a), m * __sinf(a)};
}
__device__ __forceinline__ cplx csq(cplx z) { return {fmaf(z.r, z.r, -z.i * z.i), (z.r + z.r) * z.i}; }
__device__ __forceinline__ cplx cmul(cplx a, cplx b) { return {fmaf(a.r, b.r, -a.i * b.i), fmaf(a.r, b.i, a.i * b.r)}; }
struct pair2 { __half2 re, im; };
__device__ __forceinline__ __half2 pk(cplx z) { return __floats2half2_rn(z.r, z.i); }
__device__ __forceinline__ pair2 pmul(pair2 x, __half2 z) {
  const __half2 c = __low2half2(z), s = __high2half2(z);
  return {__hfma2(x.re, c, __hneg2(__hmul2(x.im, s))), __hfma2(x.im, c, __hmul2(x.re, s))};
}
__device__ __forceinline__ pair2 pmulc(pair2 x, __half2 z) {
  const __half2 c = __low2half2(z), s = __high2half2(z);
  return {__hfma2(x.re, c, __hmul2(x.im, s)), __hfma2(x.im, c, __hneg2(__hmul2(x.re, s)))};
}
__device__ __forceinline__ uint32_t hbits(__half2 h) { return *reinterpret_cast<uint32_t*>(&h); }
__device__ __forceinline__ void put_set(uint32_t a, pair2 x0, pair2 x1, pair2 x2, pair2 x3) {
  sts128(a, hbits(x0.re), hbits(x1.re), hbits(x2.re), hbits(x3.re));
  sts128(a + 128, hbits(x0.im), hbits(x1.im), hbits(x2.im), hbits(x3.im));
}

__device__ __forceinline__ int lag_index(int l) { return l < 256 ? l : l < 512 ? 128 + (l >> 1) : 256 + (l >> 2); }

struct SsmIn { uint32_t ar, ai, br, bi, cr, ci, ldt, dsk; };
__device__ __forceinline__ SsmIn ssm_load(const Params& p, int d) {
  SsmIn in;
  const int o = d * (NST / 2) + (TID & 127);
  in.ar = __ldg(reinterpret_cast<const uint32_t*>(p.ssm[0]) + o);
  in.ai = __ldg(reinterpret_cast<const uint32_t*>(p.ssm[1]) + o);
  in.br = __ldg(reinterpret_cast<const uint32_t*>(p.ssm[2]) + o);
  in.bi = __ldg(reinterpret_cast<const uint32_t*>(p.ssm[3]) + o);
  in.cr = __ldg(reinterpret_cast<const uint32_t*>(p.ssm[4]) + o);
  in.ci = __ldg(reinterpret_cast<const uint32_t*>(p.ssm[5]) + o);
  in.ldt = __ldg(reinterpret_cast<const unsigned short*>(p.logdt) + d);
  in.dsk = __ldg(reinterpret_cast<const unsigned short*>(p.dskip) + d);
  return in;
}

__device__ __forceinline__ void range_check(int sw) {
  const int tid = TID & 127, lane = tid & 31, row = tid & 63, half = tid >> 6;
  const uint32_t st = sb + SM_ST + lane * 16;
  mbar_wait(sb + SM_BAR + B_ST, 0);
  const uint4 s0 = lds128(st), s1 = lds128(st + 512);
  mbar_wait(sb + SM_BAR + B_QB, 0);
  const uint32_t qrow = sb + SM_Q + sw * 8192 + row * 128;
  float n2 = 0.f;
#pragma unroll
  for (int c = 0; c < 4; c++) {
    const uint4 v = lds128(qrow + (((half * 4 + c) ^ (row & 7)) << 4));
    n2 = fmaf(bf_lo(v.x), bf_lo(v.x), fmaf(bf_hi(v.x), bf_hi(v.x), n2));
    n2 = fmaf(bf_lo(v.y), bf_lo(v.y), fmaf(bf_hi(v.y), bf_hi(v.y), n2));
    if (c < 3) {
      n2 = fmaf(bf_lo(v.z), bf_lo(v.z), fmaf(bf_hi(v.z), bf_hi(v.z), n2));
      n2 = fmaf(bf_lo(v.w), bf_lo(v.w), fmaf(bf_hi(v.w), bf_hi(v.w), n2));
    }
  }
  const float kn = __uint_as_float(__reduce_max_sync(~0u, max(max(s0.x, s0.z), max(s1.x, s1.z))));
  const float vm = __uint_as_float(__reduce_max_sync(~0u, max(max(s0.y, s0.w), max(s1.y, s1.w))));
  const bool ok = __all_sync(~0u, n2 * kn <= SAFE_SCORE * SAFE_SCORE && vm <= 1.0e9f && vm >= 1.0e-9f);
  if (lane == 0) {
    sts32(sb + SM_BAR + SM_FLAG + (sw * 4 + (tid >> 5)) * 4, ok);
    mbar_arrive(sb + SM_BAR + B_CHK);
  }
  __syncwarp();
}

__device__ __forceinline__ void load_u(int d, int e, uint32_t cv, uint32_t b, uint32_t kd) {
  mbar_expect(b, e >= 0 ? 4096 + 2576 : 4096);
  if (e >= 0) bulk_g2s(kd, g_kd + e * 161, 2576, b);
#pragma unroll
  for (int kc = 0; kc < 4; kc++) bulk_g2s(cv + C_U + kc * U_LBO + 17 * 16, g_uT + d * 256 + kc * 64, 1024, b);
}
__device__ __forceinline__ void load_stats() {
  mbar_expect(sb + SM_BAR + B_ST, 1024);
  bulk_g2s(sb + SM_ST, g_stat, 1024, sb + SM_BAR + B_ST);
}

__device__ __noinline__ void kgen_direct(const SsmIn in, float dt, cplx w0, cplx w1, uint32_t cv, int bar, uint32_t kd, bool wait_ka, bool exported) {
  const int tid = TID & 127;
  const uint32_t tab = cv + 4096;
  mbar_wait(sb + SM_BAR + B_XF, 0);
  sts128(tab + tid * 32, __float_as_uint(dt * bf_lo(in.ar)), __float_as_uint(dt * bf_lo(in.ai)), __float_as_uint(w0.r), __float_as_uint(w0.i));
  sts128(tab + tid * 32 + 16, __float_as_uint(dt * bf_hi(in.ar)), __float_as_uint(dt * bf_hi(in.ai)), __float_as_uint(w1.r), __float_as_uint(w1.i));
  if (wait_ka) mbar_wait(sb + SM_BAR + B_KA, 0);
  bar_sync(bar, 128);
#pragma unroll 1
  for (int i = tid; i < 641; i += 128) {
    const float l = i < 256 ? i : i < 384 ? 2 * (i - 128) : i < 512 ? 4 * (i - 256) : 8 * (i - 384);
    float k = i == 0 ? bf_lo(in.dsk) : 0.f;
#pragma unroll 1
    for (int n = 0; n < NST; n++) {
      const uint4 v = lds128(tab + n * 16);
      float turns = __uint_as_float(v.y) * l * 0.15915494309189535f;
      turns = (turns - rintf(turns)) * 6.283185307179586f;
      k = fmaf(__expf(__uint_as_float(v.x) * l), __uint_as_float(v.z) * __cosf(turns) - __uint_as_float(v.w) * __sinf(turns), k);
    }
    sts32f(kd + i * 4, k);
  }
  if (exported) fence_async_smem();
  bar_sync(bar, 128);
}

__device__ __forceinline__ void ssm_kgen(const Params& p, SsmIn& io, int next, uint32_t cv, uint32_t et, uint32_t red, int bar, uint32_t kd, bool wait_ka, bool exported) {
  const SsmIn in = io;
  uint32_t tx = TID;
  asm volatile("" : "+r"(tx), "+r"(cv), "+r"(et));
  const int tid = tx & 127, w = tid >> 5, lane = tid & 31, g = lane >> 2, t = lane & 3;
  const float dt = __bfloat162float(__float2bfloat16(expf(bf_lo(in.ldt))));
  const cplx w0 = cmul({bf_lo(in.cr), bf_lo(in.ci)}, {dt * bf_lo(in.br), dt * bf_lo(in.bi)});
  const cplx w1 = cmul({bf_hi(in.cr), bf_hi(in.ci)}, {dt * bf_hi(in.br), dt * bf_hi(in.bi)});
  const float wmx = fmaxf(fmaxf(fabsf(w0.r), fabsf(w0.i)), fmaxf(fabsf(w1.r), fabsf(w1.i)));
  const bool grow = dt * bf_lo(in.ar) > 0.f || dt * bf_hi(in.ar) > 0.f;
  const uint32_t wm = __reduce_max_sync(~0u, __float_as_uint(wmx)) | (__any_sync(~0u, grow) ? 0x80000000u : 0u);
  if (lane == 0) sts32(red + w * 4, wm);
  bar_sync(bar, 128);
  const uint4 m4 = lds128(red);
  if ((m4.x | m4.y | m4.z | m4.w) >> 31) {
    kgen_direct(in, dt, w0, w1, cv, bar, kd, wait_ka, exported);
    if (next >= 0) io = ssm_load(p, next);
    return;
  }
  const uint32_t ex = min(max(max(max(m4.x, m4.y), max(m4.z, m4.w)) >> 23, 11u), 254u);
  const float scale_in = __uint_as_float((264u - ex) << 23), scale_out = __uint_as_float((ex - 10u) << 23);

  float acc[8];
#pragma unroll
  for (int i = 0; i < 8; i++) acc[i] = 0.f;
  pin(acc);
  float k2048 = 0.f;
  const uint32_t so = (tid >> 3) * 256 + (tid & 7) * 16;
#pragma unroll 1
  for (int r = 0; r < 2; r++) {
    if (r || bar == 3) mbar_wait(sb + SM_BAR + B_XF, 0);
    const float al = dt * (r ? bf_hi(in.ar) : bf_lo(in.ar)) * 1.4426950408889634f;
    const float be = dt * (r ? bf_hi(in.ai) : bf_lo(in.ai));
    const cplx ws = {(r ? w1.r : w0.r) * scale_in, (r ? w1.i : w0.i) * scale_in};
    const cplx z1 = cseed(al, be, 1.f), z2 = csq(z1), z4 = csq(z2), z8 = csq(z4);
    const cplx z16 = cseed(al, be, 16.f), z32 = csq(z16), z64 = csq(z32), z128 = csq(z64);
    const cplx z256 = cseed(al, be, 256.f), z512 = csq(z256), z1024 = csq(z512), z2048 = csq(z1024);
    k2048 += fmaf(ws.r, z2048.r, -ws.i * z2048.i);
    const cplx wz = cmul(ws, z128);
    const __half2 h1 = pk(z1), h2 = pk(z2), h4 = pk(z4), h32 = pk(z32), h64 = pk(z64), h512 = pk(z512), h1024 = pk(z1024);
    const __half2 h16 = pk(z16), h256 = pk(z256);
    const pair2 q0 = {__floats2half2_rn(1.f, z8.r), __floats2half2_rn(0.f, z8.i)};
    const pair2 p0 = {__floats2half2_rn(ws.r, wz.r), __hneg2(__floats2half2_rn(ws.i, wz.i))};
    if (r) {
      wg_wait<0>();
      bar_sync(bar, 128);
    }
    const pair2 q1 = pmul(q0, h16), q2 = pmul(q0, h32), q3 = pmul(q1, h32);
    put_set(et + so, q0, q1, q2, q3);
    put_set(et + so + 4096, pmul(q0, h64), pmul(q1, h64), pmul(q2, h64), pmul(q3, h64));
    const pair2 p1 = pmulc(p0, h256), p2 = pmulc(p0, h512), p3 = pmulc(p1, h512);
    put_set(cv + so, p0, p1, p2, p3);
    const pair2 b0 = pmulc(p0, h4), b1 = pmulc(p1, h4);
    put_set(cv + so + 4096, b0, b1, pmulc(p2, h4), pmulc(p3, h4));
    put_set(cv + so + 8192, pmulc(p0, h1024), pmulc(p1, h1024), pmulc(p2, h1024), pmulc(p3, h1024));
    const pair2 d0 = pmulc(p0, h2), d2 = pmulc(b0, h2);
    put_set(cv + so + 12288, d0, pmulc(p1, h2), d2, pmulc(b1, h2));
    put_set(cv + so + 16384, pmulc(p0, h1), pmulc(d0, h1), pmulc(b0, h1), pmulc(d2, h1));
    fence_async_smem();
    bar_sync(bar, 128);
    uint64_t da = mkdesc(cv - 4096, 128, 4096, 0), db = mkdesc(et, 128, 4096, 0);
#pragma unroll 1
    for (int k4 = 0; k4 < 4; k4++) {
      wg_fence();
#pragma unroll
      for (int ks = 0; ks < 4; ks++) wg_h16tt(acc, da + 16 * ks, db + 16 * ks);
      wg_commit();
      da += 64;
      db += 64;
    }
  }
  if (next >= 0) io = ssm_load(p, next);
  const int k2 = __reduce_add_sync(~0u, __float2int_rn(k2048 * 4096.f));
  wg_wait<0>();
  pin(acc);
  if (lane == 0) sts32(red + 16 + w * 4, k2);
  if (wait_ka) mbar_wait(sb + SM_BAR + B_KA, 0);
  bar_sync(bar, 128);
  if (w < 3) {
    const int c0 = w == 1 ? 4 + 128 * g : 2 + (g & 4) + 128 * (g & 3);
    const int c1 = w == 0 ? 128 * g : 1 + (g & 6) + 128 * (g & 1);
    const int i0 = lag_index(c0), s0 = c0 < 256 ? 32 : c0 < 512 ? 16 : 8;
    const int i1 = w == 1 ? 512 + 16 * g : lag_index(c1), s1 = w == 1 ? 4 : c1 < 256 ? 32 : c1 < 512 ? 16 : 8;
    const uint32_t a0 = kd + i0 * 4 + 2 * t * s0, a1 = kd + i1 * 4 + 2 * t * s1;
    if (w) {
      sts32f(a0, acc[0] * scale_out);
      sts32f(a0 + s0, acc[1] * scale_out);
      sts32f(a0 + 8 * s0, acc[4] * scale_out);
      sts32f(a0 + 9 * s0, acc[5] * scale_out);
    }
    sts32f(a1, fmaf(acc[2], scale_out, tid == 0 ? bf_lo(in.dsk) : 0.f));
    sts32f(a1 + s1, acc[3] * scale_out);
    sts32f(a1 + 8 * s1, acc[6] * scale_out);
    sts32f(a1 + 9 * s1, acc[7] * scale_out);
  } else if (lane == 0) {
    const uint4 k4 = lds128(red + 16);
    sts32f(kd + 2560, ((float)(int)k4.x + (float)(int)k4.y + (float)(int)k4.z + (float)(int)k4.w) * (scale_out * (1.f / 4096.f)));
  }
  if (exported) fence_async_smem();
  bar_sync(bar, 128);
}

__device__ __forceinline__ void conv_first_load(int d, int e, uint32_t cv, int z, uint32_t kd, bool poll) {
  const int tid = TID & 127, w = warp_in_group();
  if (w == 3) {
    if (poll) {
      const uint32_t ep = read_epoch();
      cnt_wait(CT_U + (d >> 6), ep * 16);
      if (e >= 0) cnt_wait(CT_KD + e, ep);
    } else {
      mbar_wait(sb + SM_BAR + B_UOK, 0);
    }
    __syncwarp();
    if (elect_one()) {
      load_u(d, e, cv, sb + SM_BAR + B_U + z * 8, kd);
      if (z == 2) mbar_arrive(sb + SM_BAR + B_UOK);
    }
  } else if (w == 2 && z == 2 && blockIdx.x < N_ATT) {
    cnt_wait(CT_ST, read_epoch() * 32);
    __syncwarp();
    if (elect_one()) load_stats();
  }
  __syncwarp();
  if (tid < 68) {
    const int kc = (tid * 241) >> 12;
    sts128(cv + C_U + kc * (U_LBO - 272) + tid * 16, 0, 0, 0, 0);
  }
}

__device__ __forceinline__ void ssm_conv(const CUtensorMap* tmB, int d, int e, int next, int next_e, uint32_t cv, int z, uint32_t kd, uint32_t next_kd,
                                         uint32_t uphase, int check
) {
  uint32_t tx = TID;
  asm volatile("" : "+r"(tx), "+r"(cv));
  const int tid = tx & 127, w = warp_in_group(), lane = tid & 31, g = lane >> 2, t = lane & 3;
  const int bar = 1 + z;
  const uint32_t ubar = sb + SM_BAR + B_U + z * 8;
  if (e >= 0) mbar_wait(ubar, uphase & 1);

  {
    const uint32_t pt = cv + C_PT + 128;
    uint32_t q0, q1, q2, q3, q4, q5, q6, q7, dst;
    if (tid < 32) {
      uint4 a = lds128(kd + lane * 32), b = lds128(kd + lane * 32 + 16);
      float pv = lane ? lds32f(kd + lane * 32 - 4) : 0.f;
      float k0 = __uint_as_float(a.x), k1 = __uint_as_float(a.y), k2 = __uint_as_float(a.z), k3 = __uint_as_float(a.w);
      float k4 = __uint_as_float(b.x), k5 = __uint_as_float(b.y), k6 = __uint_as_float(b.z), k7 = __uint_as_float(b.w);
      q0 = pack_bf(k0, pv); q1 = pack_bf(k1, k0); q2 = pack_bf(k2, k1); q3 = pack_bf(k3, k2);
      q4 = pack_bf(k4, k3); q5 = pack_bf(k5, k4); q6 = pack_bf(k6, k5); q7 = pack_bf(k7, k6);
      dst = pt + lane * 32;
      if (lane < 8) sts128(cv + C_PT + lane * 16, 0, 0, 0, 0);
    } else if (w < 2) {
      uint4 a = lds128(kd + 1024 + lane * 16);
      float k0 = __uint_as_float(a.x), k1 = __uint_as_float(a.y), k2 = __uint_as_float(a.z), k3 = __uint_as_float(a.w);
      float k4 = lds32f(kd + 1024 + lane * 16 + 16), pv = lane ? k0 : lds32f(kd + 1020);
      q0 = pack_bf(k0, pv); q1 = pack_bf(k0, k0); q2 = pack_bf(k1, k0); q3 = pack_bf(k2, k1);
      q4 = pack_bf(k2, k2); q5 = q4; q6 = pack_bf(k3, k2); q7 = pack_bf(k4, k3);
      dst = pt + 1024 + lane * 32;
      if (lane < 16) {
        float c = lds32f(kd + 2048);
        uint32_t cc = pack_bf(c, c), c0 = pack_bf(0.f, c);
        sts128(pt + 4096 + lane * 16, lane < 2 ? cc : 0, lane == 0 ? cc : lane == 1 ? c0 : 0, lane == 0 ? cc : 0, lane == 0 ? cc : 0);
      }
    } else {
      const int n = tid - 64;
      uint2 a = lds64(kd + 1536 + n * 8);
      float k0 = __uint_as_float(a.x), k1 = __uint_as_float(a.y), k2 = lds32f(kd + 1536 + n * 8 + 8);
      q0 = pack_bf(k0, k0); q1 = q0; q2 = q0; q3 = pack_bf(k1, k0);
      q4 = pack_bf(k1, k1); q5 = q4; q6 = pack_bf(k2, k1); q7 = pack_bf(k2, k2);
      dst = pt + 2048 + n * 32;
    }
    sts128(dst, q0, q1, q2, q3);
    sts128(dst + 16, q4, q5, q6, q7);
    uint32_t pe = 0, po = 0;
    if (w >= 2) {
      const int j = tid - 64;
      uint2 a = lds64(kd + 2048 + j * 8);
      float e1 = lds32f(kd + 2056 + j * 8), o0 = lds32f(kd + 2044 + j * 8);
      pe = pack_bf(e1, j ? __uint_as_float(a.x) : 0.f);
      po = pack_bf(__uint_as_float(a.y), j ? o0 : 0.f);
    }
    sts32(cv + C_PE + tid * 4, pe);
    sts32(cv + C_PE + 512 + tid * 4, po);
  }
  mbar_wait(ubar, uphase & 1);
  TS(tsb);
  {
    auto chunk = [&](int m) { return cv + C_U + (m & 3) * U_LBO + (17 + (m >> 2)) * 16; };
    uint2 a = make_uint2(0, 0);
    uint4 b = make_uint4(0, 0, 0, 0);
    if (tid >= 2) a = lds64(chunk(tid - 2) + 8);
    if (tid >= 1) b = lds128(chunk(tid - 1));
    uint2 c = lds64(chunk(tid));
    float s[16] = {bf_lo(a.x), bf_hi(a.x), bf_lo(a.y), bf_hi(a.y), bf_lo(b.x), bf_hi(b.x), bf_lo(b.y), bf_hi(b.y),
                   bf_lo(b.z), bf_hi(b.z), bf_lo(b.w), bf_hi(b.w), bf_lo(c.x), bf_hi(c.x), bf_lo(c.y), bf_hi(c.y)};
#pragma unroll
    for (int i = 1; i < 16; i++) s[i] += s[i - 1];
    sts128(cv + C_V + 2 * V_PL + (tid & 1) * V_PL + (tid >> 1) * 16, pack_bf(s[7] - s[0], s[8] - s[1]), pack_bf(s[9] - s[2], s[10] - s[3]),
           pack_bf(s[11] - s[4], s[12] - s[5]), pack_bf(s[13] - s[6], s[14] - s[7]));
    const int n1 = (tid + 1) & 127;
    uint32_t v0 = pack_bf(s[8], s[9] - s[0]), v1 = pack_bf(s[10] - s[1], s[11] - s[2]);
    uint32_t v2 = pack_bf(s[12] - s[3], s[13] - s[4]), v3 = pack_bf(s[14] - s[5], s[15] - s[6]);
    if (n1 == 0) v0 = v1 = v2 = v3 = 0;
    sts128(cv + C_V + (n1 & 1) * V_PL + (n1 >> 1) * 16, v0, v1, v2, v3);
  }
  fence_async_smem();
  if (check >= 0) range_check(check);
  bar_sync(bar, 128);
  {
    float y3[8];
#pragma unroll
    for (int i = 0; i < 8; i++) y3[i] = 0.f;
    pin(y3);
    const uint32_t pa = cv + C_PE + (64 + 16 * w + g - 2 * t) * 4;
    const uint64_t dv = mkdesc(cv + C_V, 128, V_PL, 0);
    uint32_t re[9], ro[9];
#pragma unroll
    for (int n = 0; n < 9; n++) { re[n] = lds32(pa + 32 - 32 * n); ro[n] = lds32(pa + 512 + 32 - 32 * n); }
    wg_fence();
#pragma unroll
    for (int s = 0; s < 4; s++) {
      wg_rs16t(y3, re[2 * s + 1], re[2 * s], re[2 * s + 2], re[2 * s + 1], dv + s * 16);
      wg_rs16t(y3, ro[2 * s + 1], ro[2 * s], ro[2 * s + 2], ro[2 * s + 1], dv + s * 16 + ((2 * V_PL) >> 4));
    }
    wg_commit();
    wg_wait<0>();
    pin(y3);
    const int b3 = 16 * w + g;
    const uint32_t ya = cv + C_Y3 + ((b3 >> 1) * 36 + 16 * (b3 & 1) + 2 * t) * 4;
    sts64(ya, __float_as_uint(y3[0]), __float_as_uint(y3[1]));
    sts64(ya + 576, __float_as_uint(y3[2]), __float_as_uint(y3[3]));
    sts64(ya + 32, __float_as_uint(y3[4]), __float_as_uint(y3[5]));
    sts64(ya + 608, __float_as_uint(y3[6]), __float_as_uint(y3[7]));
  }
  bar_sync(bar, 128);
  TS(tsb + 1);
  const int h = ((w >> 1) ^ z) & 1, wb = w & 1;
  float y[32];
#pragma unroll
  for (int i = 0; i < 32; i++) y[i] = 0.f;
  if (h) {
    const uint32_t ya = cv + C_Y3 + ((2 * t - 15) * 36 + 16 * wb + g) * 4;
    if (t == 3) { y[5] = lds32f(ya + 9 * 144); y[7] = lds32f(ya + 9 * 144 + 32); }
#pragma unroll
    for (int i = 2; i < 6; i++) {
      y[4 * i] = lds32f(ya + 8 * i * 144);
      y[4 * i + 2] = lds32f(ya + 8 * i * 144 + 32);
      if (i < 5 || t < 3) { y[4 * i + 1] = lds32f(ya + (8 * i + 1) * 144); y[4 * i + 3] = lds32f(ya + (8 * i + 1) * 144 + 32); }
    }
  }
  __syncwarp();
  pin(y);
  {
    uint32_t pa = cv + C_PT + (32 + 544 * h + 16 * wb + g - 2 * t) * 4;
    uint64_t db = mkdesc(cv + C_U + 17 * 16, U_LBO, 128, 0);
    constexpr uint64_t HI = (2 * U_LBO) >> 4;
    constexpr int NB = 3, N0 = 2;
    uint32_t r[4 * NB + 1];
#pragma unroll
    for (int n = 0; n < 4 * N0 + 1; n++) r[n] = lds32(pa - 96 + 32 * n);
    wg_fence();
#pragma unroll
    for (int q = 0; q < N0; q++) {
      wg_rs64(y, r[4 * q + 1], r[4 * q + 2], r[4 * q], r[4 * q + 1], db + HI - q);
      wg_rs64(y, r[4 * q + 3], r[4 * q + 4], r[4 * q + 2], r[4 * q + 3], db - q);
    }
    wg_commit();
    wg_wait<0>();
    pa += 128 * N0 - 96;
#pragma unroll 1
    for (int it = 0; it < (17 - N0) / NB; it++) {
#pragma unroll
      for (int n = 0; n < 4 * NB + 1; n++) r[n] = lds32(pa + 32 * n);
      wg_fence();
#pragma unroll
      for (int q = 0; q < NB; q++) {
        wg_rs64(y, r[4 * q + 1], r[4 * q + 2], r[4 * q], r[4 * q + 1], db + HI - N0 - q);
        wg_rs64(y, r[4 * q + 3], r[4 * q + 4], r[4 * q + 2], r[4 * q + 3], db - N0 - q);
      }
      wg_commit();
      wg_wait<0>();
      pa += 128 * NB;
      db -= NB;
    }
    pin(y);
  }
  TS(tsb + 2);
  const uint32_t ea = cv + C_EX + (2 * t * 36 + 16 * wb + g) * 4;
  if (h) {
#pragma unroll
    for (int i = 0; i < 6; i++) {
      sts32f(ea + 8 * i * 144, y[4 * i]);
      sts32f(ea + (8 * i + 1) * 144, y[4 * i + 1]);
      sts32f(ea + 8 * i * 144 + 32, y[4 * i + 2]);
      sts32f(ea + (8 * i + 1) * 144 + 32, y[4 * i + 3]);
    }
  }
  bar_sync(bar, 128);
  if (h) {
    if (next >= 0 && wb == 0) {
      if (next_e >= 0) {
        const uint32_t ep = read_epoch();
        cnt_wait(CT_U + (next >> 6), ep * 16);
        cnt_wait(CT_KD + next_e, ep);
        __syncwarp();
      }
      if (elect_one()) load_u(next, next_e, cv, ubar, next_kd);
    }
    __syncwarp();
  } else {
#pragma unroll
    for (int i = 2; i < 8; i++) {
      if (i > 2 || t > 0) { y[4 * i] += lds32f(ea + (8 * i - 17) * 144); y[4 * i + 2] += lds32f(ea + (8 * i - 17) * 144 + 32); }
      y[4 * i + 1] += lds32f(ea + (8 * i - 16) * 144);
      y[4 * i + 3] += lds32f(ea + (8 * i - 16) * 144 + 32);
    }
    const int m = lane >> 3, c = 8 * (m >> 1) + (lane & 7);
    const uint32_t oa = cv + C_OUT + (c >> 1) * 128 + ((((c & 1) * 4 + 2 * wb + (m & 1)) ^ (d & 7) ^ (c >> 1)) << 4);
#pragma unroll
    for (int i = 0; i < 4; i++)
      stsm4t(oa + i * 1024, pack_bf(y[8 * i], y[8 * i + 1]), pack_bf(y[8 * i + 2], y[8 * i + 3]), pack_bf(y[8 * i + 4], y[8 * i + 5]), pack_bf(y[8 * i + 6], y[8 * i + 7]));
    fence_async_smem();
    bar_sync(7 + z, 64);
    if (wb == 0 && elect_one()) {
      tma2d_store(tmB, cv + C_OUT, d * 64, 0);
      bulk_drain();
      cnt_post(CT_B + d / 112);
    }
    __syncwarp();
  }
  TS(tsb + 3);
}

#define PROF_PARAM
#define PROF_ARG

template <int N> __device__ __forceinline__ void build_wkv(int c0) {
  const int u = TID & 15, k0 = (TID >> 4) + 64 * c0;
  const uint32_t src = sb + SM_RAW + (u >> 3) * RAW_V + (u & 7) * 8 + k0 * 56;
  const uint32_t dst = sb + SM_W + k0 * 128 + (((u >> 1) ^ (k0 & 7)) << 4) + (u & 1) * 8;
  if ((u & 7) < 7) {
    uint2 v[2 * N];
#pragma unroll
    for (int i = 0; i < 2 * N; i++) v[i] = lds64(src + i * 32 * 56);
#pragma unroll
    for (int i = 0; i < 2 * N; i++) sts64(dst + i * 4096, v[i].x, v[i].y);
  }
  if (c0 == 0 && TID < DM) {
    const uint32_t gw = lds32(sb + SM_RAW + RAW_G + (TID >> 1) * 4), row = sb + SM_W + TID * 128 + 8;
    sts64(row + ((3 ^ (TID & 7)) << 4), 0, 0);
    sts64(row + ((7 ^ (TID & 7)) << 4), (TID & 1) ? gw & 0xffff0000u : gw << 16, 0);
  }
  fence_async_smem();
}

__device__ __forceinline__ void kv_load(int n, int slot) {
  mbar_expect(sb + SM_BAR + B_KVF + 8 * slot, 16384);
  bulk_g2s(sb + SM_KV + slot * 16384, g_kv + n * 1024, 16384, sb + SM_BAR + B_KVF + 8 * slot);
}
__device__ __forceinline__ void load_qkv(int cta, int which) {
  constexpr uint32_t bar = sb + SM_BAR;
  const int tile = cta >> 2, hg = cta & 3;
  if (which == 0) {
    cnt_wait(CT_Q + tile, read_epoch() * 7);
    const uint32_t bytes = (hg == 0 || hg == 3) ? 16384 : 24576;
    mbar_expect(bar + B_QR, bytes);
    bulk_g2s(sb + SM_QR, g_q + (tile * 7 + ((112 * hg) >> 6)) * 512, bytes, bar + B_QR);
  } else {
    cnt_wait(CT_KV, read_epoch() * 32);
#pragma unroll 1
    for (int n = 0; n < 4; n++) kv_load(n, n);
  }
}

__device__ __forceinline__ void proj_phase(int cta, int wg PROF_PARAM) {
  const int tid = TID & 127, w = tid >> 5, lane = tid & 31, g = lane >> 2, t = lane & 3;
  const int tt = cta >> 3, j = cta & 7;
  if (j == 7) {
    mbar_wait(sb + SM_BAR + B_RAW, 0);
    build_wkv<7>(0);
    bar_sync(6, 512);
  }
  TS(2);
  float a[32];
#pragma unroll
  for (int i = 0; i < 32; i++) a[i] = 0.f;
  pin(a);
  const uint64_t dx = mkdesc(sb + SM_X + wg * 8192, 16, 1024, 1), dw = mkdesc(sb + SM_W, 16, 1024, 1);
#pragma unroll 1
  for (int i = 0; i < 7; i++) {
    int c = i + j;
    c = c >= 7 ? c - 7 : c;
    mbar_wait(sb + SM_BAR + B_CH + c * 8, 0);
    wg_fence();
#pragma unroll
    for (int k = 0; k < 4; k++) wg_ss64t(a, dx + c * 1024 + 2 * k, dw + c * 512 + 128 * k);
    wg_commit();
  }
  wg_wait<0>();
  pin(a);
  TS(3);
  uint32_t v[16];
  const float qs = j < 7 ? 0.18898223650461363f * 1.4426950408889634f : 1.f;
#pragma unroll
  for (int i = 0; i < 16; i++) v[i] = pack_bf(a[2 * i] * qs, a[2 * i + 1] * qs);
  const uint32_t z0 = v[14], z1 = v[15];
  uint32_t x6 = v[6], x7 = v[7], x14 = z0, x15 = z1;
  if (j == 7) {
    const float cm = 0.583325f;
    const float ch = __bfloat162float(__float2bfloat16(cm));
    const uint32_t c_mufu = pack_bf(ch, cm - ch), c_poly = pack_bf(65536.f, (g & 1) ? 496.f : 127.f);
    if (t >= 2) {
      x6 = ((MUFU_MASK >> (4 * w + t - 2)) & 1) ? c_mufu : c_poly;
      x7 = ((MUFU_MASK >> (4 * w + t)) & 1) ? c_mufu : c_poly;
    }
    if (t == 2) x14 = x15 = 0x00003f80u;
  }
  const uint32_t st = sb + SM_X + (j == 0 ? 65536 : 0) + wg * 8192;
  const int row = 16 * w + (lane & 15);
  const uint32_t sa = st + row * 128, sx = (lane >> 4) ^ (row & 7);
  stsm4(sa + (sx << 4), v[0], v[1], v[2], v[3]);
  stsm4(sa + ((sx ^ 2) << 4), v[4], v[5], x6, x7);
  stsm4(sa + ((sx ^ 4) << 4), v[8], v[9], v[10], v[11]);
  stsm4(sa + ((sx ^ 6) << 4), v[12], v[13], x14, x15);
  fence_async_smem();
  bar_sync(1 + wg, 128);
  if (tid == 32) {
    bulk_s2g(j < 7 ? g_q + ((2 * tt + wg) * 7 + j) * 512 : g_kv + (2 * tt + wg) * 512, st, 8192);
    bulk_drain();
    cnt_post(j < 7 ? CT_Q + 2 * tt + wg : CT_KV);
  }
  __syncwarp();
  if (j == 7) {
    float n0 = 0.f, n1 = 0.f;
    uint32_t vm = 0;
#pragma unroll
    for (int i = 0; i < 16; i++) {
      if (i < 8) {
        float& n = (i & 1) ? n1 : n0;
        n = fmaf(bf_lo(v[i]), bf_lo(v[i]), fmaf(bf_hi(v[i]), bf_hi(v[i]), n));
      } else if (i < 14 || t < 2) {
        vm = max(vm, max((v[i] << 16) & 0x7fffffffu, v[i] & 0x7fff0000u));
      }
    }
    if (t == 2) {
      const uint32_t gp = sb + SM_AUX + wg * 512 + (16 * w + g) * 4;
      sts32f(gp, __bfloat162float(__float2bfloat16(__fdividef(1.f, 1.f + __expf(-bf_hi(z0))))));
      sts32f(gp + 32, __bfloat162float(__float2bfloat16(__fdividef(1.f, 1.f + __expf(-bf_hi(z1))))));
    }
    n0 += __shfl_xor_sync(~0u, n0, 1);
    n1 += __shfl_xor_sync(~0u, n1, 1);
    n0 += __shfl_xor_sync(~0u, n0, 2);
    n1 += __shfl_xor_sync(~0u, n1, 2);
    const uint32_t kn = __reduce_max_sync(~0u, max(__float_as_uint(n0) & 0x7fffffffu, __float_as_uint(n1) & 0x7fffffffu));
    vm = __reduce_max_sync(~0u, vm);
    if (lane == 0) sts64(sb + SM_AUX + wg * 512 + 256 + w * 8, kn, vm);
    fence_async_smem();
    bar_sync(1 + wg, 128);
  }
  if (tid == 32 && j == 7) {
    bulk_s2g(g_gate + 128 * tt + 64 * wg, sb + SM_AUX + wg * 512, 256);
    bulk_s2g(g_stat + 4 * tt + 2 * wg, sb + SM_AUX + wg * 512 + 256, 32);
    bulk_drain();
    cnt_post(CT_ST);
  }
  __syncwarp();
  if (j < 7) {
    const int tok = 32 * ((lane & 7) >> 1) + 8 * w + 2 * (lane >> 3) + (lane & 1);
    const uint32_t ra = sb + SM_X + j * 16384 + tok * 128;
    uint4* dst = g_uT + (64 * j + 32 * wg + g) * 256 + w * 64 + 4 * tt + t;
#pragma unroll
    for (int cg = 0; cg < 4; cg++) {
      uint4 v;
      ldsm4t(v.x, v.y, v.z, v.w, ra + (((4 * wg + cg) ^ (tok & 7)) << 4));
      dst[cg * 8 * 256] = v;
    }
  }
  bar_sync(5, 256);
  if (TID == 224 && j < 7) {
    mbar_arrive(sb + SM_BAR + B_XF);
    cnt_signal(CT_U + j);
  }
  __syncwarp();
  TS(4);
}

__device__ __forceinline__ void load_wo(const CUtensorMap* tmWo, int hg) {
  mbar_wait(sb + SM_BAR + B_QB, 0);
  __syncwarp();
  if (elect_one()) {
    mbar_expect(sb + SM_BAR + B_WO, 86016);
#pragma unroll
    for (int i = 0; i < 6; i++) tma2d(sb + SM_WO + i * 14336, tmWo, 112 * hg + 56 * (i & 1), 112 * ((hg + (i >> 1)) & 3), sb + SM_BAR + B_WO);
  }
}

__device__ __forceinline__ uint32_t exp_mufu(float a, float b) { return pack_bf(ex2(a), ex2(b)); }
__device__ __forceinline__ uint32_t exp_packed(float a, float b, uint32_t k64k) {
  uint32_t h, m, r;
  asm("mad.lo.u32 %0, %1, %3, %2;" : "=r"(h) : "r"(__float_as_uint(b)), "r"(__float_as_uint(a)), "r"(k64k));
  asm("lop3.b32 %0, %1, 0x007f007f, %2, 0xEA;" : "=r"(m) : "r"(h), "r"(0x3f003f00u));
  asm("fma.rn.bf16x2 %0, %1, %2, %3;" : "=r"(r) : "r"(h), "r"(m), "r"(h & 0x7f807f80u));
  return r;
}
__device__ __forceinline__ void exp_tile(const float (&s)[32], uint32_t (&p)[16], uint32_t k64k) {
#pragma unroll
  for (int i = 0; i < 16; i++) p[i] = ((MUFU_MASK >> i) & 1) ? exp_mufu(s[2 * i], s[2 * i + 1]) : exp_packed(s[2 * i], s[2 * i + 1], k64k);
}
template <int OQ, int OK> __device__ __forceinline__ void qk(float (&s)[32], uint64_t dq, uint64_t dk) {
  wg_ss64_z(s, dq + OQ, dk + OK);
  wg_ss64(s, dq + OQ + 2, dk + OK + 2);
}
template <int OK> __device__ __forceinline__ void pv(float (&o)[16], const uint32_t (&p)[16], uint64_t dk) {
#pragma unroll
  for (int k = 0; k < 4; k++) wg_rs32t(o, p[4 * k], p[4 * k + 1], p[4 * k + 2], p[4 * k + 3], dk + OK + 4 + 128 * k);
}

__device__ __forceinline__ void kv_refill(int n, int slot) {
  mbar_wait(sb + SM_BAR + B_KVE + 8 * slot, ((n - 1) >> 2) & 1);
  if (elect_one()) kv_load(n + 3, slot);
  __syncwarp();
}

__device__ __forceinline__ void load_wo3(const CUtensorMap* tmWo, int hg) {
  mbar_wait(sb + SM_BAR + B_S13, 0);
  mbar_expect(sb + SM_BAR + B_WO3, 28672);
  tma2d(sb + SM_WO3, tmWo, 112 * hg, 112 * ((hg + 3) & 3), sb + SM_BAR + B_WO3);
  tma2d(sb + SM_WO3 + 14336, tmWo, 112 * hg + 56, 112 * ((hg + 3) & 3), sb + SM_BAR + B_WO3);
}

template <int ST>
__device__ __forceinline__ bool attn_stage(int it, int warp, bool lead, uint32_t k64k, uint64_t dq, uint64_t& dk, float (&sa)[32], float (&sc)[32],
                                           uint32_t (&pa)[16], uint32_t (&pb)[16], float (&oa)[16], float (&ob)[16]) {
  constexpr int SN = (ST + 1) & 3, PREV = (ST + 3) & 3, CUR = ST * 1024, NXT = SN * 1024;
  const int n = it * 4 + ST;
  asm volatile("" : "+l"(dk));
  wg_fence();
  pv<CUR>(oa, pa, dk);
  qk<0, CUR + 512>(sa, dq, dk);
  wg_commit();
  wg_wait<1>();
  pin(sc);
  mbar_arrive_if(sb + SM_BAR + (ST == 2 && it == 3 ? B_S13 : B_KVE + 8 * PREV), lead && n > 0);
  exp_tile(sc, pb, k64k);
  wg_fence();
  pv<CUR>(ob, pb, dk);
  qk<4, CUR + 512>(sc, dq, dk);
  wg_commit();
  wg_wait<1>();
  pin(sa);
  exp_tile(sa, pa, k64k);
  if (ST == 3 && it == 3) return true;
  mbar_wait(sb + SM_BAR + B_KVF + 8 * SN, (ST == 3 ? it + 1 : it) & 1);
  wg_fence();
  pv<CUR + 512>(oa, pa, dk);
  qk<0, NXT>(sa, dq, dk);
  wg_commit();
  wg_wait<1>();
  pin(sc);
  exp_tile(sc, pb, k64k);
  wg_fence();
  pv<CUR + 512>(ob, pb, dk);
  qk<4, NXT>(sc, dq, dk);
  wg_commit();
  if (warp == 2 * ST + (it & 1) && n >= 1 && n < 13) kv_refill(n, PREV);
  wg_wait<1>();
  pin(sa);
  exp_tile(sa, pa, k64k);
  return false;
}

__device__ __forceinline__ void attn_fast(const Params& p, int wg, int warp, float (&oa)[16], float (&ob)[16]) {
  const uint64_t dq = mkdesc(sb + SM_Q + wg * 8192, 16, 1024, 1);
  uint64_t dk = mkdesc(sb + SM_KV + blockIdx.y, 16, 1024, 1);
  const uint32_t k64k = p.k64k;
  const bool lead = (TID & 31) == 0;
  float sa[32], sc[32];
  uint32_t pa[16], pb[16];
  wg_fence();
  qk<0, 0>(sa, dq, dk);
  wg_commit();
  qk<4, 0>(sc, dq, dk);
  wg_commit();
  wg_wait<1>();
  pin(sa);
  exp_tile(sa, pa, k64k);
#pragma unroll 1
  for (int it = 0; it < 4; it++) {
    attn_stage<0>(it, warp, lead, k64k, dq, dk, sa, sc, pa, pb, oa, ob);
    attn_stage<1>(it, warp, lead, k64k, dq, dk, sa, sc, pa, pb, oa, ob);
    attn_stage<2>(it, warp, lead, k64k, dq, dk, sa, sc, pa, pb, oa, ob);
    if (attn_stage<3>(it, warp, lead, k64k, dq, dk, sa, sc, pa, pb, oa, ob)) break;
  }
  wg_fence();
  pv<3 * 1024 + 512>(oa, pa, dk);
  wg_commit();
  wg_wait<1>();
  pin(sc);
  exp_tile(sc, pb, k64k);
  wg_fence();
  pv<3 * 1024 + 512>(ob, pb, dk);
  wg_commit();
  wg_wait<0>();
  pin(oa);
  pin(ob);
}

__device__ __forceinline__ void safe_step(float (&o)[16], float& m0, float& m1, uint64_t dq, uint64_t dk) {
  float s[32];
  uint32_t p[16];
  wg_fence();
  qk<0, 0>(s, dq, dk);
  wg_commit();
  wg_wait<0>();
  pin(s);
  float n0 = m0, n1 = m1;
#pragma unroll
  for (int i = 0; i < 8; i++) {
    n0 = fmaxf(n0, fmaxf(s[4 * i], s[4 * i + 1]));
    n1 = fmaxf(n1, fmaxf(s[4 * i + 2], s[4 * i + 3]));
  }
  n0 = fmaxf(n0, __shfl_xor_sync(~0u, n0, 1));
  n0 = fmaxf(n0, __shfl_xor_sync(~0u, n0, 2));
  n1 = fmaxf(n1, __shfl_xor_sync(~0u, n1, 1));
  n1 = fmaxf(n1, __shfl_xor_sync(~0u, n1, 2));
  const float c0 = ex2(m0 - n0), c1 = ex2(m1 - n1);
  m0 = n0;
  m1 = n1;
#pragma unroll
  for (int i = 0; i < 4; i++) { o[4 * i] *= c0; o[4 * i + 1] *= c0; o[4 * i + 2] *= c1; o[4 * i + 3] *= c1; }
#pragma unroll
  for (int i = 0; i < 8; i++) {
    p[2 * i] = exp_mufu(s[4 * i] - n0, s[4 * i + 1] - n0);
    p[2 * i + 1] = exp_mufu(s[4 * i + 2] - n1, s[4 * i + 3] - n1);
  }
  pin(o);
  wg_fence();
  pv<0>(o, p, dk);
  wg_commit();
  wg_wait<0>();
  pin(o);
}
__device__ __forceinline__ void attn_safe(int wg, float (&oa)[16], float (&ob)[16]) {
  const uint64_t dqa = mkdesc(sb + SM_Q + wg * 8192, 16, 1024, 1), dk = mkdesc(sb + SM_KV + 32768, 16, 1024, 1);
  float ma0 = -3.0e38f, ma1 = -3.0e38f, mb0 = -3.0e38f, mb1 = -3.0e38f;
#pragma unroll 1
  for (int n = 0; n < 32; n++) {
    if (!(n & 1)) {
      bar_sync(5, 256);
      if (TID == 0) kv_load(n >> 1, 2 + ((n >> 1) & 1));
      __syncwarp();
      mbar_wait(sb + SM_BAR + B_KVF + 16 + 8 * ((n >> 1) & 1), (n >> 2) & 1);
    }
    safe_step(oa, ma0, ma1, dqa, dk + (n & 3) * 512);
    safe_step(ob, mb0, mb1, dqa + 4, dk + (n & 3) * 512);
  }
}

__device__ __forceinline__ void stage_o(const float (&o)[16], uint32_t img, int c0, int t) {
  const int src = (TID & 28) | 2;
  const float i0 = __fdividef(1.f, __shfl_sync(~0u, o[12], src)), i1 = __fdividef(1.f, __shfl_sync(~0u, o[14], src));
  const int c = c0 + 2 * t;
  const uint32_t a = img + (c >> 3) * 1024 + (c & 7) * 2;
#pragma unroll
  for (int i = 0; i < 4; i++) {
    if (i < 3 || t < 2) {
      sts32(a + i * 1024, pack_bf(o[4 * i] * i0, o[4 * i + 1] * i0));
      sts32(a + i * 1024 + 128, pack_bf(o[4 * i + 2] * i1, o[4 * i + 3] * i1));
    }
  }
}

__device__ __forceinline__ void attention_phase(const Params& p, int cta, int wg PROF_PARAM) {
  const int tid = TID & 127, w = tid >> 5, lane = tid & 31, g = lane >> 2, t = lane & 3;
  const int tile = cta >> 2, hg = cta & 3, b0 = (112 * hg) >> 6, r0 = 16 * w + g;
  const int warp = __shfl_sync(~0u, TID >> 5, 0);
  constexpr uint32_t bar = sb + SM_BAR;
  mbar_wait(bar + B_QR, 0);
  TS(5);
  const uint32_t qi = sb + SM_Q + wg * 8192 + r0 * 128 + t * 4;
#pragma unroll
  for (int m = 0; m < 2; m++) {
    const int c0 = DH * (4 * hg + 2 * wg + m) - 64 * b0 + 2 * t;
#pragma unroll
    for (int i = 0; i < 4; i++) {
      const int c = c0 + 8 * i;
      const uint32_t a = sb + SM_QR + (c >> 6) * 8192 + r0 * 128 + ((((c >> 3) & 7) ^ g) << 4) + (c & 7) * 2;
      uint32_t v0 = t == 2 ? 0x3f803f80u : 0u, v1 = t == 3 ? 0x3f803f80u : 0u;
      if (i < 3 || t < 2) { v0 = lds32(a); v1 = lds32(a + 1024); }
      sts32(qi + (((4 * m + i) ^ g) << 4), v0);
      sts32(qi + (((4 * m + i) ^ g) << 4) + 1024, v1);
    }
  }
  fence_async_smem();
  bar_sync(1 + wg, 128);
  mbar_arrive_if(bar + B_QB, tid == 64);
  mbar_wait(bar + B_KVF, 0);
  float oa[16], ob[16];
#pragma unroll
  for (int i = 0; i < 16; i++) oa[i] = ob[i] = 0.f;
  pin(oa);
  pin(ob);
  TS(6);
  attn_fast(p, wg, warp, oa, ob);
  mbar_wait(bar + B_CHK, 0);
  const uint4 f0 = lds128(bar + SM_FLAG), f1 = lds128(bar + SM_FLAG + 16);
  if (!(f0.x & f0.y & f0.z & f0.w & f1.x & f1.y & f1.z & f1.w)) {
    bar_sync(5, 256);
    if (t >= 2) {
#pragma unroll
      for (int m = 0; m < 2; m++) {
        sts32(qi + (((4 * m + 3) ^ g) << 4), 0);
        sts32(qi + (((4 * m + 3) ^ g) << 4) + 1024, 0);
      }
    }
    fence_async_smem();
#pragma unroll
    for (int i = 0; i < 16; i++) oa[i] = ob[i] = 0.f;
    pin(oa);
    pin(ob);
    attn_safe(wg, oa, ob);
  }
  TS(7);
  const uint32_t own = sb + SM_OWN + wg * 7168;
  bar_sync(1 + wg, 128);
  stage_o(oa, own + r0 * 16, 0, t);
  stage_o(ob, own + r0 * 16, DH, t);
  fence_async_smem();
  bar_sync(1 + wg, 128);
  if (tid == 0) {
    bulk_s2g(g_o + (tile * 4 + hg) * 896 + wg * 448, own, 7168);
    asm volatile("cp.async.bulk.commit_group;" ::: "memory");
    asm volatile("cp.async.bulk.wait_group 0;" ::: "memory");
    cnt_post(CT_O + tile);
  }
  __syncwarp();
  bar_sync(5, 256);
  TS(8);

  float acc[28];
#pragma unroll
  for (int i = 0; i < 28; i++) acc[i] = 0.f;
  pin(acc);
  float mix[28], g0, g1;
  const uint64_t db = mkdesc(sb + SM_WO + wg * 14336, 16, 1024, 1);
  mbar_wait(bar + B_WO, 0);
#pragma unroll 1
  for (int s = 0; s < 4; s++) {
    if (s) mbar_wait(bar + B_O + 8 * (s - 1), 0);
    if (s == 3) mbar_wait(bar + B_WO3, 0);
    const uint64_t da = mkdesc(sb + (s ? SM_OR + (s - 1) * 14336 : SM_OWN), 1024, 128, 0);
    const uint64_t dw = db + (s < 3 ? s * 1792 : SM_WO3 >> 4);
    wg_fence();
#pragma unroll
    for (int k = 0; k < 7; k++) wg_ss56t(acc, da + 128 * k, dw + 128 * k);
    wg_commit();
    if (s == 0) {
      if (TID == 160) {
        cnt_wait(CT_O + tile, read_epoch() * 8);
#pragma unroll 1
        for (int u = 0; u < 3; u++) {
          mbar_expect(bar + B_O + 8 * u, 14336);
          bulk_g2s(sb + SM_OR + u * 14336, g_o + (tile * 4 + ((hg + 1 + u) & 3)) * 896, 14336, bar + B_O + 8 * u);
        }
      }
      __syncwarp();
    }
  }
  TS(9);
  {
    mbar_wait(bar + B_BT, 0);
    uint32_t b[16];
    const int m = lane >> 3, r = lane & 7;
    const uint32_t ba = sb + SM_BT + (56 * wg + 8 * (m >> 1) + r) * 128 + (((2 * w + (m & 1)) ^ r) << 4);
#pragma unroll
    for (int i = 0; i < 4; i++) ldsm4t(b[4 * i], b[4 * i + 1], b[4 * i + 2], b[4 * i + 3], ba + (i < 3 || m < 2 ? i * 2048 : 0));
    g0 = lds32f(sb + SM_G + r0 * 4);
    g1 = lds32f(sb + SM_G + r0 * 4 + 32);
    const float h0 = __bfloat162float(__float2bfloat16(1.f - g0)), h1 = __bfloat162float(__float2bfloat16(1.f - g1));
#pragma unroll
    for (int i = 0; i < 7; i++) {
      mix[4 * i] = h0 * bf_lo(b[2 * i]);
      mix[4 * i + 1] = h0 * bf_hi(b[2 * i]);
      mix[4 * i + 2] = h1 * bf_lo(b[2 * i + 1]);
      mix[4 * i + 3] = h1 * bf_hi(b[2 * i + 1]);
    }
  }
  wg_wait<0>();
  pin(acc);
  TS(10);
  uint32_t b[14];
#pragma unroll
  for (int i = 0; i < 7; i++) {
    b[2 * i] = pack_bf(fmaf(g0, acc[4 * i], mix[4 * i]), fmaf(g0, acc[4 * i + 1], mix[4 * i + 1]));
    b[2 * i + 1] = pack_bf(fmaf(g1, acc[4 * i + 2], mix[4 * i + 2]), fmaf(g1, acc[4 * i + 3], mix[4 * i + 3]));
  }
  const uint32_t ob0 = sb + SM_OUT + wg * 7168, oad = ob0 + (16 * w + (lane & 15)) * 112 + (lane >> 4) * 16;
#pragma unroll
  for (int i = 0; i < 3; i++) stsm4(oad + i * 32, b[4 * i], b[4 * i + 1], b[4 * i + 2], b[4 * i + 3]);
  asm volatile("stmatrix.sync.aligned.m8n8.x2.shared.b16 [%0], {%1,%2};" ::"r"(ob0 + (16 * w + (lane & 15)) * 112 + 96), "r"(b[12]), "r"(b[13]) : "memory");
  __syncwarp();
  uint4* op = reinterpret_cast<uint4*>(p.out) + (64 * tile + 16 * w) * (DM / 8) + 14 * hg + 7 * wg;
#pragma unroll
  for (int i = 0; i < 4; i++) {
    const int e = lane + 32 * i, row = (e * 147) >> 10;
    if (i < 3 || lane < 16) op[row * (DM / 8) + e - 7 * row] = lds128(ob0 + w * 1792 + e * 16);
  }
  TS(11);
}

__global__ void __launch_bounds__(512, 1)
fused_kernel(const __grid_constant__ CUtensorMap tmX, const __grid_constant__ CUtensorMap tmWq, const __grid_constant__ CUtensorMap tmWo,
             const __grid_constant__ CUtensorMap tmB, const __grid_constant__ Params p) {
  extern __shared__ __align__(1024) uint8_t smem_raw[];
  constexpr uint32_t bar = sb + SM_BAR;
  const int cta = blockIdx.x, tt = cta >> 3, j = cta & 7;
  const int warp0 = __shfl_sync(~0u, TID >> 5, 0), wg = warp0 >> 2;
  const int qi = 7 * tt + j, d0 = 4 * qi;
  const bool extra = cta >= N_ATT;
  SsmIn in = {};

  if (warp0 == 0) {
    if (elect_one()) {
#pragma unroll
      for (int i = 0; i < 7; i++) mbar_init(bar + B_CH + 8 * i, 1);
      mbar_init(bar + B_RAW, 1);
      fence_mbar_init();
      if (j == 7 && !extra) {
        mbar_expect(bar + B_RAW, 2 * 25088 + 896);
        bulk_g2s(sb + SM_RAW, p.wk, 25088, bar + B_RAW);
        bulk_g2s(sb + SM_RAW + RAW_V, p.wv, 25088, bar + B_RAW);
        bulk_g2s(sb + SM_RAW + RAW_G, p.gatew, 896, bar + B_RAW);
      }
    }
    __syncwarp();
    asm volatile("bar.arrive 0, 512;" ::: "memory");
    if (j < 7) {
      const long long t0 = clock64();
      while (clock64() - t0 < LOAD_DELAY) {}
    }
#pragma unroll 1
    for (int i = 0; i < (extra ? 0 : 7); i++) {
      int c = i + j;
      c = c >= 7 ? c - 7 : c;
      if (elect_one()) {
        mbar_expect(bar + B_CH + 8 * c, j < 7 ? 24576 : 16384);
        tma2d(sb + SM_X + c * 16384, &tmX, 64 * c, 128 * tt, bar + B_CH + 8 * c);
        if (j < 7) tma2d(sb + SM_W + c * 8192, &tmWq, 64 * j, 64 * c, bar + B_CH + 8 * c);
      }
      __syncwarp();
    }
  } else {
    if (warp0 == 1) {
      if (elect_one()) {
#pragma unroll
        for (int i = 0; i < 4; i++) { mbar_init(bar + B_KVF + 8 * i, 1); mbar_init(bar + B_KVE + 8 * i, 8); }
#pragma unroll
        for (int i = 0; i < 3; i++) mbar_init(bar + B_O + 8 * i, 1);
#pragma unroll
        for (int i = 0; i < 4; i++) mbar_init(bar + B_U + 8 * i, 1);
        mbar_init(bar + B_KA, 1);
        mbar_init(bar + B_KH, 1);
        mbar_init(bar + B_UOK, 1);
        mbar_init(bar + B_QR, 1);
        mbar_init(bar + B_WO, 1);
        mbar_init(bar + B_BT, 1);
        mbar_init(bar + B_EPOCH, 1);
        mbar_init(bar + B_QB, 2);
        mbar_init(bar + B_CHK, 8);
        mbar_init(bar + B_ST, 1);
        mbar_init(bar + B_XF, 1);
        mbar_init(bar + B_WO3, 1);
        mbar_init(bar + B_S13, 8);
        fence_mbar_init();
      }
    } else if (wg >= 2 && j < 7 && !extra) {
      in = ssm_load(p, wg == 2 ? d0 : d0 + 3);
      const int i = TID & 127;
      if (i < 24) asm volatile("prefetch.global.L2 [%0];" ::"l"(p.ssm[i >> 2] + (d0 + wg - 1) * NST + (i & 3) * 64));
    }
    __syncwarp();
    bar_sync(0, 512);
  }
  if ((uint32_t)__cvta_generic_to_shared(smem_raw) != sb) __trap();
  TS(1);

  if (TID == 96) {
    sts32(bar + SM_EPOCH, atomicAdd(&g_cnt[CT_TICKET], 1u) / N_CTA);
    mbar_arrive(bar + B_EPOCH);
  }
  __syncwarp();
  if (wg < 2 && !extra) {
    asm volatile("setmaxnreg.inc.sync.aligned.u32 160;");
    proj_phase(cta, wg PROF_ARG);
    if ((TID & 127) == 0) load_qkv(cta, wg);
    __syncwarp();
    TS(12);
    attention_phase(p, cta, wg PROF_ARG);
  } else {
    asm volatile("setmaxnreg.dec.sync.aligned.u32 96;");
    const uint32_t cv = sb + (extra ? wg * SSM_WG : SM_SSM + (wg & 1) * SSM_WG);
    const bool gen = j < 7 && !extra;
    if (gen) {
      const int nk = wg == 2 ? 1 : 3;
#pragma unroll 1
      for (int r = 0; r < nk; r++) {
        const bool hand = wg == 3 && r == 1;
        ssm_kgen(p, in, r + 1 < nk ? d0 + 1 + r : -1, cv, r == 2 ? sb + SM_E2 : cv + C_E, sb + SM_RED + (wg & 1) * 32, 1 + wg, hand ? cv - SSM_WG + C_KD2 : cv + C_KD, hand,
                 wg == 3 && r == 0);
        TS(2 + (r ? 1 : 0));
        if ((TID & 127) == 0) {
          if (wg == 2) mbar_arrive(bar + B_KA);
          else if (r == 1) mbar_arrive(bar + B_KH);
          else if (r == 0) {
            bulk_s2g(g_kd + qi * 161, cv + C_KD, 2576);
            bulk_drain();
            cnt_post(CT_KD + qi);
          }
        }
        if (r == 2 && warp0 == 15) load_wo(&tmWo, cta & 3);
        __syncwarp();
        if (hand) conv_first_load(d0 + 2, -1, cv, 3, 0, false);
      }
    } else if (!extra) {
      mbar_wait(bar + B_RAW, 0);
      build_wkv<7>(0);
      bar_sync(6, 512);
    }
    const int nc = extra ? 3 : (gen && wg == 3) ? 1 : 2;
    const int e0 = extra ? 64 + 12 * (cta - N_ATT) + wg : 4 * tt + (wg & 1), es = extra ? 4 : 2;
    if (!gen || wg == 2) conv_first_load(gen ? d0 : 4 * e0 + 3, gen ? -1 : e0, cv, wg, cv + C_KD, true);
#pragma unroll 1
    for (int r = 0; r < nc; r++) {
      const int e = gen ? -1 : e0 + es * r, ne = gen ? -1 : e + es;
      const int d = gen ? d0 + (wg == 2 ? r : 2) : 4 * e + 3;
      const int nd = r + 1 == nc ? -1 : gen ? d + 1 : 4 * ne + 3;
      if (gen && r) mbar_wait(bar + B_KH, 0);
      ssm_conv(&tmB, d, e, nd, ne, cv, wg, cv + (r == 0 ? C_KD : r == 1 ? C_KD2 : C_KD3), cv + (r == 0 ? C_KD2 : C_KD3), r, extra ? -1 : gen ? (wg == 2 ? r : -1) : r ? -1 : wg & 1
      );
      if (!gen && !extra && r == 0 && warp0 == 13) load_wo(&tmWo, cta & 3);
      __syncwarp();
    }
    if (extra) return;
    bar_sync(1 + wg, 128);
    if ((TID & 127) == 0) {
      if (wg == 3) load_wo3(&tmWo, cta & 3);
      if (wg == 2) {
        const int tile = cta >> 2, hg = cta & 3;
        const uint32_t e = read_epoch();
        cnt_wait(CT_B + hg, e * 112);
        fence_async_smem();
        mbar_expect(bar + B_BT, 14336 + 256);
        bulk_g2s(sb + SM_BT, g_bT + (tile * DM + 112 * hg) * 8, 14336, bar + B_BT);
        bulk_g2s(sb + SM_G, g_gate + 64 * tile, 256, bar + B_BT);
      }
    }
  }
}

typedef CUresult (*EncodeFn)(CUtensorMap*, CUtensorMapDataType, cuuint32_t, void*, const cuuint64_t*, const cuuint64_t*, const cuuint32_t*,
                             const cuuint32_t*, CUtensorMapInterleave, CUtensorMapSwizzle, CUtensorMapL2promotion, CUtensorMapFloatOOBfill);

void encode_map(EncodeFn enc, CUtensorMap* m, void* ptr, int cols, int rows, int box_cols, int box_rows, CUtensorMapSwizzle sw) {
  cuuint64_t dims[2] = {(cuuint64_t)cols, (cuuint64_t)rows}, strides[1] = {(cuuint64_t)cols * 2};
  cuuint32_t box[2] = {(cuuint32_t)box_cols, (cuuint32_t)box_rows}, es[2] = {1, 1};
  enc(m, CU_TENSOR_MAP_DATA_TYPE_BFLOAT16, 2, ptr, dims, strides, box, es, CU_TENSOR_MAP_INTERLEAVE_NONE, sw,
      CU_TENSOR_MAP_L2_PROMOTION_L2_128B, CU_TENSOR_MAP_FLOAT_OOB_FILL_NONE);
}

}

extern "C" void kernel_launch(void* const* d_in, const int* in_sizes, int n_in, void* d_out, int out_size) {
  static EncodeFn enc = nullptr;
  if (!enc) {
    cudaDriverEntryPointQueryResult q;
    cudaGetDriverEntryPoint("cuTensorMapEncodeTiled", (void**)&enc, cudaEnableDefault, &q);
    cudaFuncSetAttribute(fused_kernel, cudaFuncAttributeMaxDynamicSharedMemorySize, SM_TOTAL);
  }
  CUtensorMap tmX, tmWq, tmWo, tmB;
  void* bt = nullptr;
  cudaGetSymbolAddress(&bt, g_bT);
  encode_map(enc, &tmB, bt, DM * 64, 32, 64, 32, CU_TENSOR_MAP_SWIZZLE_128B);
  encode_map(enc, &tmX, d_in[0], DM, SEQ, 64, 128, CU_TENSOR_MAP_SWIZZLE_128B);
  encode_map(enc, &tmWq, d_in[1], DM, DM, 64, 64, CU_TENSOR_MAP_SWIZZLE_128B);
  encode_map(enc, &tmWo, d_in[4], DM, DM, 64, 112, CU_TENSOR_MAP_SWIZZLE_128B);
  typedef const __nv_bfloat16* bp;
  Params p = {{(bp)d_in[6], (bp)d_in[7], (bp)d_in[8], (bp)d_in[9], (bp)d_in[10], (bp)d_in[11]},
              (bp)d_in[2], (bp)d_in[3], (bp)d_in[12], (bp)d_in[13], (bp)d_in[14], (__nv_bfloat16*)d_out, 65536u};
  fused_kernel<<<N_CTA, 512, SM_TOTAL, cudaStreamPerThread>>>(tmX, tmWq, tmWo, tmB, p);
}
```
